```python
import torch

def _softmax(x, axis=-1):
    return torch.softmax(x, dim=axis)
def _gelu(x):
    return torch.nn.functional.gelu(x, approximate="tanh")
def _silu(x):
    return torch.nn.functional.silu(x)
def _sigmoid(x):
    return torch.sigmoid(x)
def _layernorm(x, axis=-1, eps=1e-5):
    m = x.mean(dim=axis, keepdim=True)
    v = x.var(dim=axis, keepdim=True, unbiased=False)
    return (x - m) / torch.sqrt(v + eps)
def _scatter_add(tgt, idx, src, axis=0):
    return tgt.clone().index_add_(axis, idx, src)
def _segment_sum(src, seg, n):
    out = torch.zeros((n,) + src.shape[1:], dtype=src.dtype)
    return out.index_add_(0, seg, src)
def _pad(x, pw):
    flat = tuple(v for pair in reversed(pw) for v in pair)
    return torch.nn.functional.pad(x, flat)

kernel_name = 'gated_mix__spectral_fnet__dense_activation_relu__prompt'

def setup_inputs():

    _w = (lambda a: (lambda t: t.to(torch.bfloat16) if t.is_floating_point() else t)(torch.as_tensor(a)))
    def _A_setup():
        B, S, D = 1, 2048, 512
        ns = torch.arange(S)[:, None] * torch.arange(S)[None, :]
        nd = torch.arange(D)[:, None] * torch.arange(D)[None, :]
        Ws_re = torch.cos(-2.0 * torch.pi * ns / S).to(float)
        Ws_im = torch.sin(-2.0 * torch.pi * ns / S).to(float)
        Wd_re = torch.cos(-2.0 * torch.pi * nd / D).to(float)
        Wd_im = torch.sin(-2.0 * torch.pi * nd / D).to(float)
        return {
            "x": _w((lambda *s: torch.randn(*s, dtype=torch.bfloat16) * 0.05)(B, S, D)),
            "dft_seq_re": _w(Ws_re),
            "dft_seq_im": _w(Ws_im),
            "dft_hid_re": _w(Wd_re),
            "dft_hid_im": _w(Wd_im),
        }
    _A_in = _A_setup()

    def _B_setup():
        B, S, D, Dff = 1, 2048, 512, 1376
        return {
            "x": _w((lambda *s: torch.randn(*s, dtype=torch.bfloat16) * 0.05)(B, S, D)),
            "w1": _w((lambda *s: torch.randn(*s, dtype=torch.bfloat16) * 1.6)(D, Dff)),
            "w2": _w((lambda *s: torch.randn(*s, dtype=torch.bfloat16) * 1.6)(Dff, D)),
        }
    _B_in = _B_setup()

    return {
        "A_x": _A_in["x"],
        "A_dft_seq_re": _A_in["dft_seq_re"],
        "A_dft_seq_im": _A_in["dft_seq_im"],
        "A_dft_hid_re": _A_in["dft_hid_re"],
        "A_dft_hid_im": _A_in["dft_hid_im"],
        "B_x": _B_in["x"],
        "B_w1": _B_in["w1"],
        "B_w2": _B_in["w2"],
        "gate_w": _w((lambda *s: torch.randn(*s, dtype=torch.bfloat16) * 0.05)(512) * 16.0),
    }

def reference(A_x, A_dft_seq_re, A_dft_seq_im, A_dft_hid_re, A_dft_hid_im, B_x, B_w1, B_w2, gate_w):
    def _A_ref(x, dft_seq_re, dft_seq_im, dft_hid_re, dft_hid_im):
        a = torch.einsum("bsd,ed->bse", x, dft_hid_re)
        b = torch.einsum("bsd,ed->bse", x, dft_hid_im)
        y = torch.einsum("ts,bse->bte", dft_seq_re, a) - torch.einsum("ts,bse->bte", dft_seq_im, b)
        return y

    def _B_ref(x, w1, w2):
        h = torch.einsum("bsd,df->bsf", x, w1)
        zero = torch.zeros_like(h)
        h = torch.maximum(h, zero)
        return torch.einsum("bsf,fd->bsd", h, w2)

    x = A_x
    g = _sigmoid((x * gate_w).sum(-1, keepdims=True))
    a = _A_ref(x, A_dft_seq_re, A_dft_seq_im, A_dft_hid_re, A_dft_hid_im)
    b = _B_ref(x, B_w1, B_w2)
    return g * a + (1 - g) * b
```

```cpp
#include <cuda_runtime.h>
#include <cuda_bf16.h>
#include <cuda.h>
#include <stdint.h>

namespace {

constexpr int S_ = 2048, D_ = 512, F_ = 1376;
constexpr int NX = 6, NB = 4;
constexpr int XS = 16384, BS = 32768, VS = 24576;
constexpr int OFF_X = NB * BS;
constexpr int OFF_BAR = OFF_X + NX * XS;
constexpr int OFF_G = OFF_BAR + 768;
constexpr int SMEM_USED = OFF_G + 512;
constexpr int SMEM_BYTES = SMEM_USED + 1024;
constexpr int B_FA1 = 0, B_FV = 8, B_DONE = 16, B_FX = 32, B_EX = 38, B_FB = 44, B_EB = 48, B_FLAGA = 52, B_G = 60, B_GD = 61,
              B_PART = 62, B_STAB = 63, B_PUB = 64, B_AB = 65, B_SND = 67, B_H = 73, B_HF = 76, B_FLAGH = 79, B_ISS = 80, NBAR = 83;
constexpr unsigned SPIN_LIMIT = 1u << 16;
constexpr int REG_P = 72, REG_C = 216;
constexpr int PFW_START = 4000;
constexpr int PACE0 = 1200, PACE = 550;
constexpr int STAG = 800;
constexpr int PUBG = 4, STABG = 2;
constexpr int A_LEAD = 2;
constexpr int HS0 = 2, HSS = 2;
constexpr int H_CH = 8192;

__device__ __forceinline__ int passItem(int pass, int b) { return pass == 0 ? b : (b + 2) % 5; }

constexpr int cslotB(int i) { return (i & 3) == 3 ? 3 : ((i & 3) + 1) % 3; }
constexpr int cslotX(int i) { return i == 16 ? 1 : ((i - (i > 16)) % 5 + 2) % 6; }
constexpr unsigned long long packB(int lo) {
    unsigned long long v = 0;
    for (int i = 0; i < 16; i++) {
        int n = 0;
        for (int k = 0; k < lo + i; k++) n += cslotB(k) == cslotB(lo + i);
        v |= (unsigned long long)(cslotB(lo + i) | ((n & 1) << 3)) << (4 * i);
    }
    return v;
}
constexpr unsigned long long packX(int lo) {
    unsigned long long v = 0;
    for (int i = 0; i < 16; i++) {
        int n = 0;
        for (int k = 0; k < lo + i; k++) n += cslotX(k) == cslotX(lo + i);
        v |= (unsigned long long)(cslotX(lo + i) | ((n & 1) << 3)) << (4 * i);
    }
    return v;
}
constexpr unsigned long long PB0 = packB(0), PB1 = packB(16), PX0 = packX(0), PX1 = packX(16);
__device__ __forceinline__ int entB(int i) { return (int)((i < 16 ? PB0 >> (4 * i) : PB1 >> (4 * (i - 16))) & 15); }
__device__ __forceinline__ int entX(int i) { return (int)((i < 16 ? PX0 >> (4 * i) : PX1 >> (4 * (i - 16))) & 15); }
__device__ __forceinline__ int slotB(int i) { return entB(i) & 7; }
__device__ __forceinline__ int slotX(int i) { return entX(i) & 7; }
__device__ __forceinline__ int nthB(int i) { return entB(i) >> 3; }
__device__ __forceinline__ int nthX(int i) { return entX(i) >> 3; }

constexpr unsigned long long STEPS = 0xFEDCBA7659432180ull;
constexpr unsigned W_UNIT = 0xB972DB94u, W_PRE = 0x321FFFFFu, V_UNIT = 0x4DA74D46u, V_PRE = 0xBA98641Fu;
constexpr int XL_K = 7, XL_PRE = 5, AB_STEP = 10;
constexpr int OFF_V = OFF_X - 2 * XS;
constexpr unsigned X_PRE = 0xFEEDCu;
__device__ __forceinline__ int nib(unsigned t, int k) { return (t >> (4 * k)) & 15; }
__device__ __forceinline__ bool stepIsA(int st) { return !((STEPS >> (4 * st)) & 8); }
__device__ __forceinline__ int stepK(int st) { return (int)(STEPS >> (4 * st)) & 7; }
__device__ __forceinline__ int stageOff(int i) { return OFF_X + slotX(i == 0 ? 13 : 15 + i) * XS; }

__device__ __align__(1024) unsigned char g_ab[64 * 8 * 8192];
__device__ __align__(1024) unsigned char g_h[128 * 3 * 16384];
__device__ __align__(1024) uint2 g_gate[S_];
__device__ unsigned g_flagAB[128 * 32];
__device__ unsigned g_flagH[128 * 32];
__device__ unsigned g_epoch[128 * 32];

__device__ __forceinline__ uint32_t s2u(const void* p) { return (uint32_t)__cvta_generic_to_shared(p); }
__device__ __forceinline__ void mbar_init(uint32_t b, int c) { asm volatile("mbarrier.init.shared::cta.b64 [%0], %1;" ::"r"(b), "r"(c) : "memory"); }
__device__ __forceinline__ void mbar_expect(uint32_t b, int bytes) { asm volatile("mbarrier.arrive.expect_tx.shared::cta.b64 _, [%0], %1;" ::"r"(b), "r"(bytes) : "memory"); }
__device__ __forceinline__ void mbar_arrive(uint32_t b) { asm volatile("mbarrier.arrive.shared::cta.b64 _, [%0];" ::"r"(b) : "memory"); }
__device__ __forceinline__ void mbar_arrive_cta(uint32_t b, uint32_t cta) {
    asm volatile("{\n.reg .b32 ra;\nmapa.shared::cluster.u32 ra, %0, %1;\nmbarrier.arrive.shared::cluster.b64 _, [ra];\n}" ::"r"(b), "r"(cta) : "memory");
}
__device__ __forceinline__ void mbar_wait(uint32_t b, uint32_t parity) {
    asm volatile("{\n.reg .pred p;\n.reg .u32 n;\nmov.u32 n, 0;\n"
                 "WL:\nmbarrier.try_wait.parity.shared::cta.b64 p, [%0], %1;\n@p bra WD;\n"
                 "add.u32 n, n, 1;\nsetp.lt.u32 p, n, 0x4000;\n@p bra WL;\nWD:\n}" ::"r"(b), "r"(parity) : "memory");
}
__device__ __forceinline__ void tma2d(uint32_t dst, const CUtensorMap* m, int c0, int c1, uint32_t bar) {
    asm volatile("cp.async.bulk.tensor.2d.shared::cluster.global.mbarrier::complete_tx::bytes [%0], [%1, {%3, %4}], [%2];"
                 ::"r"(dst), "l"(m), "r"(bar), "r"(c0), "r"(c1) : "memory");
}
__device__ __forceinline__ void tma2d_mc(uint32_t dst, const CUtensorMap* m, int c0, int c1, uint32_t bar) {
    asm volatile("cp.async.bulk.tensor.2d.shared::cluster.global.mbarrier::complete_tx::bytes.multicast::cluster [%0], [%1, {%3, %4}], [%2], %5;"
                 ::"r"(dst), "l"(m), "r"(bar), "r"(c0), "r"(c1), "h"((uint16_t)3) : "memory");
}
__device__ __forceinline__ void tma2d_red(const CUtensorMap* m, int c0, int c1, uint32_t src) {
    asm volatile("cp.reduce.async.bulk.tensor.2d.global.shared::cta.add.tile.bulk_group [%0, {%2, %3}], [%1];" ::"l"(m), "r"(src), "r"(c0), "r"(c1) : "memory");
}
__device__ __forceinline__ void bulk_load(uint32_t dst, const void* src, int bytes, uint32_t bar) {
    asm volatile("cp.async.bulk.shared::cluster.global.mbarrier::complete_tx::bytes [%0], [%1], %2, [%3];"
                 ::"r"(dst), "l"(src), "r"(bytes), "r"(bar) : "memory");
}
__device__ __forceinline__ void bulk_load_mc(uint32_t dst, const void* src, int bytes, uint32_t bar) {
    asm volatile("cp.async.bulk.shared::cluster.global.mbarrier::complete_tx::bytes.multicast::cluster [%0], [%1], %2, [%3], %4;"
                 ::"r"(dst), "l"(src), "r"(bytes), "r"(bar), "h"((uint16_t)3) : "memory");
}
__device__ __forceinline__ void bulk_store(void* dst, uint32_t src, int bytes) {
    asm volatile("cp.async.bulk.global.shared::cta.bulk_group [%0], [%1], %2;" ::"l"(dst), "r"(src), "r"(bytes) : "memory");
}
__device__ __forceinline__ void bulk_commit() { asm volatile("cp.async.bulk.commit_group;" ::: "memory"); }
__device__ __forceinline__ void bulk_wait_read() { asm volatile("cp.async.bulk.wait_group.read 0;" ::: "memory"); }
__device__ __forceinline__ void bulk_wait_all() { asm volatile("cp.async.bulk.wait_group 0;" ::: "memory"); }
__device__ __forceinline__ void fence_proxy_async_smem() { asm volatile("fence.proxy.async.shared::cta;" ::: "memory"); }
__device__ __forceinline__ void stsm4(uint32_t addr, uint32_t r0, uint32_t r1, uint32_t r2, uint32_t r3) {
    asm volatile("stmatrix.sync.aligned.m8n8.x4.shared.b16 [%0], {%1, %2, %3, %4};" ::"r"(addr), "r"(r0), "r"(r1), "r"(r2), "r"(r3) : "memory");
}
__device__ __forceinline__ void ldsm4(uint32_t addr, uint32_t& r0, uint32_t& r1, uint32_t& r2, uint32_t& r3) {
    asm volatile("ldmatrix.sync.aligned.m8n8.x4.shared.b16 {%0, %1, %2, %3}, [%4];" : "=r"(r0), "=r"(r1), "=r"(r2), "=r"(r3) : "r"(addr) : "memory");
}
__device__ __forceinline__ void prefetch_map(const CUtensorMap* m) { asm volatile("prefetch.tensormap [%0];" ::"l"(m) : "memory"); }
__device__ __forceinline__ unsigned ld_acquire(const unsigned* p) {
    unsigned v; asm volatile("ld.acquire.gpu.global.u32 %0, [%1];" : "=r"(v) : "l"(p) : "memory"); return v;
}
__device__ __forceinline__ void publish(unsigned* p, unsigned v) {
    asm volatile("fence.acq_rel.gpu;\nst.relaxed.gpu.global.u32 [%0], %1;" ::"l"(p), "r"(v) : "memory");
}
__device__ __forceinline__ uint4 ld_b128(const void* p) {
    uint4 r;
    asm volatile("{\n.reg .b128 t;\n.reg .b64 lo, hi;\nld.relaxed.gpu.global.b128 t, [%4];\nmov.b128 {lo, hi}, t;\n"
                 "mov.b64 {%0, %1}, lo;\nmov.b64 {%2, %3}, hi;\n}" : "=r"(r.x), "=r"(r.y), "=r"(r.z), "=r"(r.w) : "l"(p) : "memory");
    return r;
}
__device__ __forceinline__ void sleep_until(long long t) { while (clock64() < t) __nanosleep(64); }
__device__ __forceinline__ void fence_proxy_async_global() { asm volatile("fence.proxy.async.global;" ::: "memory"); }
__device__ __forceinline__ void bar_sync(int id, int n) { asm volatile("bar.sync %0, %1;" ::"r"(id), "r"(n) : "memory"); }
__device__ __forceinline__ void wg_fence() { asm volatile("wgmma.fence.sync.aligned;" ::: "memory"); }
__device__ __forceinline__ void wg_commit() { asm volatile("wgmma.commit_group.sync.aligned;" ::: "memory"); }
template <int N> __device__ __forceinline__ void wg_wait() { asm volatile("wgmma.wait_group.sync.aligned %0;" ::"n"(N) : "memory"); }
template <int LO, int HI, int N> __device__ __forceinline__ void reg_pin(float (&d)[N]) {
#pragma unroll
    for (int i = LO; i < HI; i++) asm volatile("" : "+f"(d[i])::"memory");
}
__device__ __forceinline__ uint32_t pack_bf16(float lo, float hi) {
    uint32_t r; asm("cvt.rn.bf16x2.f32 %0, %1, %2;" : "=r"(r) : "f"(hi), "f"(lo)); return r;
}
__device__ __forceinline__ uint32_t pack_bf16_relu(float lo, float hi) {
    uint32_t r; asm("cvt.rn.relu.bf16x2.f32 %0, %1, %2;" : "=r"(r) : "f"(hi), "f"(lo)); return r;
}
__device__ __forceinline__ float bf16r(float v) { return __bfloat162float(__float2bfloat16_rn(v)); }
__device__ __forceinline__ float bf_lo(uint32_t w) { return __uint_as_float(w << 16); }
__device__ __forceinline__ float bf_hi(uint32_t w) { return __uint_as_float(w & 0xFFFF0000u); }
__device__ __forceinline__ uint64_t mk_desc(uint32_t addr, uint32_t lbo, uint32_t sbo) {
    return (uint64_t)((addr & 0x3FFFF) >> 4) | ((uint64_t)(lbo >> 4) << 16) | ((uint64_t)(sbo >> 4) << 32) | (1ull << 62);
}

template <int TB, int O, int N>
__device__ __forceinline__ void wgmma_n128_z(float (&d)[N], uint64_t da, int oa, uint64_t db, int ob) {
    asm volatile("{\n.reg .b64 a, b;\nadd.u64 a, %64, %65;\nadd.u64 b, %66, %67;\n"
        "wgmma.mma_async.sync.aligned.m64n128k16.f32.bf16.bf16 "
        "{%0, %1, %2, %3, %4, %5, %6, %7, %8, %9, %10, %11, %12, %13, %14, %15, "
        "%16, %17, %18, %19, %20, %21, %22, %23, %24, %25, %26, %27, %28, %29, %30, %31, "
        "%32, %33, %34, %35, %36, %37, %38, %39, %40, %41, %42, %43, %44, %45, %46, %47, "
        "%48, %49, %50, %51, %52, %53, %54, %55, %56, %57, %58, %59, %60, %61, %62, %63}, "
        "a, b, 0, 1, 1, 0, %68;\n}\n"
        : "=f"(d[O + 0]), "=f"(d[O + 1]), "=f"(d[O + 2]), "=f"(d[O + 3]), "=f"(d[O + 4]), "=f"(d[O + 5]), "=f"(d[O + 6]), "=f"(d[O + 7]),
          "=f"(d[O + 8]), "=f"(d[O + 9]), "=f"(d[O + 10]), "=f"(d[O + 11]), "=f"(d[O + 12]), "=f"(d[O + 13]), "=f"(d[O + 14]), "=f"(d[O + 15]),
          "=f"(d[O + 16]), "=f"(d[O + 17]), "=f"(d[O + 18]), "=f"(d[O + 19]), "=f"(d[O + 20]), "=f"(d[O + 21]), "=f"(d[O + 22]), "=f"(d[O + 23]),
          "=f"(d[O + 24]), "=f"(d[O + 25]), "=f"(d[O + 26]), "=f"(d[O + 27]), "=f"(d[O + 28]), "=f"(d[O + 29]), "=f"(d[O + 30]), "=f"(d[O + 31]),
          "=f"(d[O + 32]), "=f"(d[O + 33]), "=f"(d[O + 34]), "=f"(d[O + 35]), "=f"(d[O + 36]), "=f"(d[O + 37]), "=f"(d[O + 38]), "=f"(d[O + 39]),
          "=f"(d[O + 40]), "=f"(d[O + 41]), "=f"(d[O + 42]), "=f"(d[O + 43]), "=f"(d[O + 44]), "=f"(d[O + 45]), "=f"(d[O + 46]), "=f"(d[O + 47]),
          "=f"(d[O + 48]), "=f"(d[O + 49]), "=f"(d[O + 50]), "=f"(d[O + 51]), "=f"(d[O + 52]), "=f"(d[O + 53]), "=f"(d[O + 54]), "=f"(d[O + 55]),
          "=f"(d[O + 56]), "=f"(d[O + 57]), "=f"(d[O + 58]), "=f"(d[O + 59]), "=f"(d[O + 60]), "=f"(d[O + 61]), "=f"(d[O + 62]), "=f"(d[O + 63])
        : "l"(da), "l"((uint64_t)(oa >> 4)), "l"(db), "l"((uint64_t)(ob >> 4)), "n"(TB));
}
template <int TB, int O, int N>
__device__ __forceinline__ void wgmma_n128_a(float (&d)[N], uint64_t da, int oa, uint64_t db, int ob) {
    asm volatile("{\n.reg .b64 a, b;\nadd.u64 a, %64, %65;\nadd.u64 b, %66, %67;\n"
        "wgmma.mma_async.sync.aligned.m64n128k16.f32.bf16.bf16 "
        "{%0, %1, %2, %3, %4, %5, %6, %7, %8, %9, %10, %11, %12, %13, %14, %15, "
        "%16, %17, %18, %19, %20, %21, %22, %23, %24, %25, %26, %27, %28, %29, %30, %31, "
        "%32, %33, %34, %35, %36, %37, %38, %39, %40, %41, %42, %43, %44, %45, %46, %47, "
        "%48, %49, %50, %51, %52, %53, %54, %55, %56, %57, %58, %59, %60, %61, %62, %63}, "
        "a, b, 1, 1, 1, 0, %68;\n}\n"
        : "+f"(d[O + 0]), "+f"(d[O + 1]), "+f"(d[O + 2]), "+f"(d[O + 3]), "+f"(d[O + 4]), "+f"(d[O + 5]), "+f"(d[O + 6]), "+f"(d[O + 7]),
          "+f"(d[O + 8]), "+f"(d[O + 9]), "+f"(d[O + 10]), "+f"(d[O + 11]), "+f"(d[O + 12]), "+f"(d[O + 13]), "+f"(d[O + 14]), "+f"(d[O + 15]),
          "+f"(d[O + 16]), "+f"(d[O + 17]), "+f"(d[O + 18]), "+f"(d[O + 19]), "+f"(d[O + 20]), "+f"(d[O + 21]), "+f"(d[O + 22]), "+f"(d[O + 23]),
          "+f"(d[O + 24]), "+f"(d[O + 25]), "+f"(d[O + 26]), "+f"(d[O + 27]), "+f"(d[O + 28]), "+f"(d[O + 29]), "+f"(d[O + 30]), "+f"(d[O + 31]),
          "+f"(d[O + 32]), "+f"(d[O + 33]), "+f"(d[O + 34]), "+f"(d[O + 35]), "+f"(d[O + 36]), "+f"(d[O + 37]), "+f"(d[O + 38]), "+f"(d[O + 39]),
          "+f"(d[O + 40]), "+f"(d[O + 41]), "+f"(d[O + 42]), "+f"(d[O + 43]), "+f"(d[O + 44]), "+f"(d[O + 45]), "+f"(d[O + 46]), "+f"(d[O + 47]),
          "+f"(d[O + 48]), "+f"(d[O + 49]), "+f"(d[O + 50]), "+f"(d[O + 51]), "+f"(d[O + 52]), "+f"(d[O + 53]), "+f"(d[O + 54]), "+f"(d[O + 55]),
          "+f"(d[O + 56]), "+f"(d[O + 57]), "+f"(d[O + 58]), "+f"(d[O + 59]), "+f"(d[O + 60]), "+f"(d[O + 61]), "+f"(d[O + 62]), "+f"(d[O + 63])
        : "l"(da), "l"((uint64_t)(oa >> 4)), "l"(db), "l"((uint64_t)(ob >> 4)), "n"(TB));
}
template <int TB, int O, int N>
__device__ __forceinline__ void wgmma_n176_z(float (&d)[N], uint64_t da, int oa, uint64_t db, int ob) {
    asm volatile("{\n.reg .b64 a, b;\nadd.u64 a, %88, %89;\nadd.u64 b, %90, %91;\n"
        "wgmma.mma_async.sync.aligned.m64n176k16.f32.bf16.bf16 "
        "{%0, %1, %2, %3, %4, %5, %6, %7, %8, %9, %10, %11, %12, %13, %14, %15, "
        "%16, %17, %18, %19, %20, %21, %22, %23, %24, %25, %26, %27, %28, %29, %30, %31, "
        "%32, %33, %34, %35, %36, %37, %38, %39, %40, %41, %42, %43, %44, %45, %46, %47, "
        "%48, %49, %50, %51, %52, %53, %54, %55, %56, %57, %58, %59, %60, %61, %62, %63, "
        "%64, %65, %66, %67, %68, %69, %70, %71, %72, %73, %74, %75, %76, %77, %78, %79, "
        "%80, %81, %82, %83, %84, %85, %86, %87}, "
        "a, b, 0, 1, 1, 0, %92;\n}\n"
        : "=f"(d[O + 0]), "=f"(d[O + 1]), "=f"(d[O + 2]), "=f"(d[O + 3]), "=f"(d[O + 4]), "=f"(d[O + 5]), "=f"(d[O + 6]), "=f"(d[O + 7]),
          "=f"(d[O + 8]), "=f"(d[O + 9]), "=f"(d[O + 10]), "=f"(d[O + 11]), "=f"(d[O + 12]), "=f"(d[O + 13]), "=f"(d[O + 14]), "=f"(d[O + 15]),
          "=f"(d[O + 16]), "=f"(d[O + 17]), "=f"(d[O + 18]), "=f"(d[O + 19]), "=f"(d[O + 20]), "=f"(d[O + 21]), "=f"(d[O + 22]), "=f"(d[O + 23]),
          "=f"(d[O + 24]), "=f"(d[O + 25]), "=f"(d[O + 26]), "=f"(d[O + 27]), "=f"(d[O + 28]), "=f"(d[O + 29]), "=f"(d[O + 30]), "=f"(d[O + 31]),
          "=f"(d[O + 32]), "=f"(d[O + 33]), "=f"(d[O + 34]), "=f"(d[O + 35]), "=f"(d[O + 36]), "=f"(d[O + 37]), "=f"(d[O + 38]), "=f"(d[O + 39]),
          "=f"(d[O + 40]), "=f"(d[O + 41]), "=f"(d[O + 42]), "=f"(d[O + 43]), "=f"(d[O + 44]), "=f"(d[O + 45]), "=f"(d[O + 46]), "=f"(d[O + 47]),
          "=f"(d[O + 48]), "=f"(d[O + 49]), "=f"(d[O + 50]), "=f"(d[O + 51]), "=f"(d[O + 52]), "=f"(d[O + 53]), "=f"(d[O + 54]), "=f"(d[O + 55]),
          "=f"(d[O + 56]), "=f"(d[O + 57]), "=f"(d[O + 58]), "=f"(d[O + 59]), "=f"(d[O + 60]), "=f"(d[O + 61]), "=f"(d[O + 62]), "=f"(d[O + 63]),
          "=f"(d[O + 64]), "=f"(d[O + 65]), "=f"(d[O + 66]), "=f"(d[O + 67]), "=f"(d[O + 68]), "=f"(d[O + 69]), "=f"(d[O + 70]), "=f"(d[O + 71]),
          "=f"(d[O + 72]), "=f"(d[O + 73]), "=f"(d[O + 74]), "=f"(d[O + 75]), "=f"(d[O + 76]), "=f"(d[O + 77]), "=f"(d[O + 78]), "=f"(d[O + 79]),
          "=f"(d[O + 80]), "=f"(d[O + 81]), "=f"(d[O + 82]), "=f"(d[O + 83]), "=f"(d[O + 84]), "=f"(d[O + 85]), "=f"(d[O + 86]), "=f"(d[O + 87])
        : "l"(da), "l"((uint64_t)(oa >> 4)), "l"(db), "l"((uint64_t)(ob >> 4)), "n"(TB));
}
template <int TB, int O, int N>
__device__ __forceinline__ void wgmma_n176_a(float (&d)[N], uint64_t da, int oa, uint64_t db, int ob) {
    asm volatile("{\n.reg .b64 a, b;\nadd.u64 a, %88, %89;\nadd.u64 b, %90, %91;\n"
        "wgmma.mma_async.sync.aligned.m64n176k16.f32.bf16.bf16 "
        "{%0, %1, %2, %3, %4, %5, %6, %7, %8, %9, %10, %11, %12, %13, %14, %15, "
        "%16, %17, %18, %19, %20, %21, %22, %23, %24, %25, %26, %27, %28, %29, %30, %31, "
        "%32, %33, %34, %35, %36, %37, %38, %39, %40, %41, %42, %43, %44, %45, %46, %47, "
        "%48, %49, %50, %51, %52, %53, %54, %55, %56, %57, %58, %59, %60, %61, %62, %63, "
        "%64, %65, %66, %67, %68, %69, %70, %71, %72, %73, %74, %75, %76, %77, %78, %79, "
        "%80, %81, %82, %83, %84, %85, %86, %87}, "
        "a, b, 1, 1, 1, 0, %92;\n}\n"
        : "+f"(d[O + 0]), "+f"(d[O + 1]), "+f"(d[O + 2]), "+f"(d[O + 3]), "+f"(d[O + 4]), "+f"(d[O + 5]), "+f"(d[O + 6]), "+f"(d[O + 7]),
          "+f"(d[O + 8]), "+f"(d[O + 9]), "+f"(d[O + 10]), "+f"(d[O + 11]), "+f"(d[O + 12]), "+f"(d[O + 13]), "+f"(d[O + 14]), "+f"(d[O + 15]),
          "+f"(d[O + 16]), "+f"(d[O + 17]), "+f"(d[O + 18]), "+f"(d[O + 19]), "+f"(d[O + 20]), "+f"(d[O + 21]), "+f"(d[O + 22]), "+f"(d[O + 23]),
          "+f"(d[O + 24]), "+f"(d[O + 25]), "+f"(d[O + 26]), "+f"(d[O + 27]), "+f"(d[O + 28]), "+f"(d[O + 29]), "+f"(d[O + 30]), "+f"(d[O + 31]),
          "+f"(d[O + 32]), "+f"(d[O + 33]), "+f"(d[O + 34]), "+f"(d[O + 35]), "+f"(d[O + 36]), "+f"(d[O + 37]), "+f"(d[O + 38]), "+f"(d[O + 39]),
          "+f"(d[O + 40]), "+f"(d[O + 41]), "+f"(d[O + 42]), "+f"(d[O + 43]), "+f"(d[O + 44]), "+f"(d[O + 45]), "+f"(d[O + 46]), "+f"(d[O + 47]),
          "+f"(d[O + 48]), "+f"(d[O + 49]), "+f"(d[O + 50]), "+f"(d[O + 51]), "+f"(d[O + 52]), "+f"(d[O + 53]), "+f"(d[O + 54]), "+f"(d[O + 55]),
          "+f"(d[O + 56]), "+f"(d[O + 57]), "+f"(d[O + 58]), "+f"(d[O + 59]), "+f"(d[O + 60]), "+f"(d[O + 61]), "+f"(d[O + 62]), "+f"(d[O + 63]),
          "+f"(d[O + 64]), "+f"(d[O + 65]), "+f"(d[O + 66]), "+f"(d[O + 67]), "+f"(d[O + 68]), "+f"(d[O + 69]), "+f"(d[O + 70]), "+f"(d[O + 71]),
          "+f"(d[O + 72]), "+f"(d[O + 73]), "+f"(d[O + 74]), "+f"(d[O + 75]), "+f"(d[O + 76]), "+f"(d[O + 77]), "+f"(d[O + 78]), "+f"(d[O + 79]),
          "+f"(d[O + 80]), "+f"(d[O + 81]), "+f"(d[O + 82]), "+f"(d[O + 83]), "+f"(d[O + 84]), "+f"(d[O + 85]), "+f"(d[O + 86]), "+f"(d[O + 87])
        : "l"(da), "l"((uint64_t)(oa >> 4)), "l"(db), "l"((uint64_t)(ob >> 4)), "n"(TB));
}
template <int TB, int O, int N>
__device__ __forceinline__ void wgmma_n256_a(float (&d)[N], uint64_t da, int oa, uint64_t db, int ob) {
    asm volatile("{\n.reg .b64 a, b;\nadd.u64 a, %128, %129;\nadd.u64 b, %130, %131;\n"
        "wgmma.mma_async.sync.aligned.m64n256k16.f32.bf16.bf16 "
        "{%0, %1, %2, %3, %4, %5, %6, %7, %8, %9, %10, %11, %12, %13, %14, %15, "
        "%16, %17, %18, %19, %20, %21, %22, %23, %24, %25, %26, %27, %28, %29, %30, %31, "
        "%32, %33, %34, %35, %36, %37, %38, %39, %40, %41, %42, %43, %44, %45, %46, %47, "
        "%48, %49, %50, %51, %52, %53, %54, %55, %56, %57, %58, %59, %60, %61, %62, %63, "
        "%64, %65, %66, %67, %68, %69, %70, %71, %72, %73, %74, %75, %76, %77, %78, %79, "
        "%80, %81, %82, %83, %84, %85, %86, %87, %88, %89, %90, %91, %92, %93, %94, %95, "
        "%96, %97, %98, %99, %100, %101, %102, %103, %104, %105, %106, %107, %108, %109, %110, %111, "
        "%112, %113, %114, %115, %116, %117, %118, %119, %120, %121, %122, %123, %124, %125, %126, %127}, "
        "a, b, 1, 1, 1, 0, %132;\n}\n"
        : "+f"(d[O + 0]), "+f"(d[O + 1]), "+f"(d[O + 2]), "+f"(d[O + 3]), "+f"(d[O + 4]), "+f"(d[O + 5]), "+f"(d[O + 6]), "+f"(d[O + 7]),
          "+f"(d[O + 8]), "+f"(d[O + 9]), "+f"(d[O + 10]), "+f"(d[O + 11]), "+f"(d[O + 12]), "+f"(d[O + 13]), "+f"(d[O + 14]), "+f"(d[O + 15]),
          "+f"(d[O + 16]), "+f"(d[O + 17]), "+f"(d[O + 18]), "+f"(d[O + 19]), "+f"(d[O + 20]), "+f"(d[O + 21]), "+f"(d[O + 22]), "+f"(d[O + 23]),
          "+f"(d[O + 24]), "+f"(d[O + 25]), "+f"(d[O + 26]), "+f"(d[O + 27]), "+f"(d[O + 28]), "+f"(d[O + 29]), "+f"(d[O + 30]), "+f"(d[O + 31]),
          "+f"(d[O + 32]), "+f"(d[O + 33]), "+f"(d[O + 34]), "+f"(d[O + 35]), "+f"(d[O + 36]), "+f"(d[O + 37]), "+f"(d[O + 38]), "+f"(d[O + 39]),
          "+f"(d[O + 40]), "+f"(d[O + 41]), "+f"(d[O + 42]), "+f"(d[O + 43]), "+f"(d[O + 44]), "+f"(d[O + 45]), "+f"(d[O + 46]), "+f"(d[O + 47]),
          "+f"(d[O + 48]), "+f"(d[O + 49]), "+f"(d[O + 50]), "+f"(d[O + 51]), "+f"(d[O + 52]), "+f"(d[O + 53]), "+f"(d[O + 54]), "+f"(d[O + 55]),
          "+f"(d[O + 56]), "+f"(d[O + 57]), "+f"(d[O + 58]), "+f"(d[O + 59]), "+f"(d[O + 60]), "+f"(d[O + 61]), "+f"(d[O + 62]), "+f"(d[O + 63]),
          "+f"(d[O + 64]), "+f"(d[O + 65]), "+f"(d[O + 66]), "+f"(d[O + 67]), "+f"(d[O + 68]), "+f"(d[O + 69]), "+f"(d[O + 70]), "+f"(d[O + 71]),
          "+f"(d[O + 72]), "+f"(d[O + 73]), "+f"(d[O + 74]), "+f"(d[O + 75]), "+f"(d[O + 76]), "+f"(d[O + 77]), "+f"(d[O + 78]), "+f"(d[O + 79]),
          "+f"(d[O + 80]), "+f"(d[O + 81]), "+f"(d[O + 82]), "+f"(d[O + 83]), "+f"(d[O + 84]), "+f"(d[O + 85]), "+f"(d[O + 86]), "+f"(d[O + 87]),
          "+f"(d[O + 88]), "+f"(d[O + 89]), "+f"(d[O + 90]), "+f"(d[O + 91]), "+f"(d[O + 92]), "+f"(d[O + 93]), "+f"(d[O + 94]), "+f"(d[O + 95]),
          "+f"(d[O + 96]), "+f"(d[O + 97]), "+f"(d[O + 98]), "+f"(d[O + 99]), "+f"(d[O + 100]), "+f"(d[O + 101]), "+f"(d[O + 102]), "+f"(d[O + 103]),
          "+f"(d[O + 104]), "+f"(d[O + 105]), "+f"(d[O + 106]), "+f"(d[O + 107]), "+f"(d[O + 108]), "+f"(d[O + 109]), "+f"(d[O + 110]), "+f"(d[O + 111]),
          "+f"(d[O + 112]), "+f"(d[O + 113]), "+f"(d[O + 114]), "+f"(d[O + 115]), "+f"(d[O + 116]), "+f"(d[O + 117]), "+f"(d[O + 118]), "+f"(d[O + 119]),
          "+f"(d[O + 120]), "+f"(d[O + 121]), "+f"(d[O + 122]), "+f"(d[O + 123]), "+f"(d[O + 124]), "+f"(d[O + 125]), "+f"(d[O + 126]), "+f"(d[O + 127])
        : "l"(da), "l"((uint64_t)(oa >> 4)), "l"(db), "l"((uint64_t)(ob >> 4)), "n"(TB));
}
template <int TB, int O, int N>
__device__ __forceinline__ void wgmma_rs256_z(float (&d)[N], uint32_t a0, uint32_t a1, uint32_t a2, uint32_t a3, uint64_t db, int ob) {
    asm volatile("{\n.reg .b64 b;\nadd.u64 b, %132, %133;\n"
        "wgmma.mma_async.sync.aligned.m64n256k16.f32.bf16.bf16 "
        "{%0, %1, %2, %3, %4, %5, %6, %7, %8, %9, %10, %11, %12, %13, %14, %15, "
        "%16, %17, %18, %19, %20, %21, %22, %23, %24, %25, %26, %27, %28, %29, %30, %31, "
        "%32, %33, %34, %35, %36, %37, %38, %39, %40, %41, %42, %43, %44, %45, %46, %47, "
        "%48, %49, %50, %51, %52, %53, %54, %55, %56, %57, %58, %59, %60, %61, %62, %63, "
        "%64, %65, %66, %67, %68, %69, %70, %71, %72, %73, %74, %75, %76, %77, %78, %79, "
        "%80, %81, %82, %83, %84, %85, %86, %87, %88, %89, %90, %91, %92, %93, %94, %95, "
        "%96, %97, %98, %99, %100, %101, %102, %103, %104, %105, %106, %107, %108, %109, %110, %111, "
        "%112, %113, %114, %115, %116, %117, %118, %119, %120, %121, %122, %123, %124, %125, %126, %127}, "
        "{%128, %129, %130, %131}, b, 0, 1, 1, %134;\n}\n"
        : "=f"(d[O + 0]), "=f"(d[O + 1]), "=f"(d[O + 2]), "=f"(d[O + 3]), "=f"(d[O + 4]), "=f"(d[O + 5]), "=f"(d[O + 6]), "=f"(d[O + 7]),
          "=f"(d[O + 8]), "=f"(d[O + 9]), "=f"(d[O + 10]), "=f"(d[O + 11]), "=f"(d[O + 12]), "=f"(d[O + 13]), "=f"(d[O + 14]), "=f"(d[O + 15]),
          "=f"(d[O + 16]), "=f"(d[O + 17]), "=f"(d[O + 18]), "=f"(d[O + 19]), "=f"(d[O + 20]), "=f"(d[O + 21]), "=f"(d[O + 22]), "=f"(d[O + 23]),
          "=f"(d[O + 24]), "=f"(d[O + 25]), "=f"(d[O + 26]), "=f"(d[O + 27]), "=f"(d[O + 28]), "=f"(d[O + 29]), "=f"(d[O + 30]), "=f"(d[O + 31]),
          "=f"(d[O + 32]), "=f"(d[O + 33]), "=f"(d[O + 34]), "=f"(d[O + 35]), "=f"(d[O + 36]), "=f"(d[O + 37]), "=f"(d[O + 38]), "=f"(d[O + 39]),
          "=f"(d[O + 40]), "=f"(d[O + 41]), "=f"(d[O + 42]), "=f"(d[O + 43]), "=f"(d[O + 44]), "=f"(d[O + 45]), "=f"(d[O + 46]), "=f"(d[O + 47]),
          "=f"(d[O + 48]), "=f"(d[O + 49]), "=f"(d[O + 50]), "=f"(d[O + 51]), "=f"(d[O + 52]), "=f"(d[O + 53]), "=f"(d[O + 54]), "=f"(d[O + 55]),
          "=f"(d[O + 56]), "=f"(d[O + 57]), "=f"(d[O + 58]), "=f"(d[O + 59]), "=f"(d[O + 60]), "=f"(d[O + 61]), "=f"(d[O + 62]), "=f"(d[O + 63]),
          "=f"(d[O + 64]), "=f"(d[O + 65]), "=f"(d[O + 66]), "=f"(d[O + 67]), "=f"(d[O + 68]), "=f"(d[O + 69]), "=f"(d[O + 70]), "=f"(d[O + 71]),
          "=f"(d[O + 72]), "=f"(d[O + 73]), "=f"(d[O + 74]), "=f"(d[O + 75]), "=f"(d[O + 76]), "=f"(d[O + 77]), "=f"(d[O + 78]), "=f"(d[O + 79]),
          "=f"(d[O + 80]), "=f"(d[O + 81]), "=f"(d[O + 82]), "=f"(d[O + 83]), "=f"(d[O + 84]), "=f"(d[O + 85]), "=f"(d[O + 86]), "=f"(d[O + 87]),
          "=f"(d[O + 88]), "=f"(d[O + 89]), "=f"(d[O + 90]), "=f"(d[O + 91]), "=f"(d[O + 92]), "=f"(d[O + 93]), "=f"(d[O + 94]), "=f"(d[O + 95]),
          "=f"(d[O + 96]), "=f"(d[O + 97]), "=f"(d[O + 98]), "=f"(d[O + 99]), "=f"(d[O + 100]), "=f"(d[O + 101]), "=f"(d[O + 102]), "=f"(d[O + 103]),
          "=f"(d[O + 104]), "=f"(d[O + 105]), "=f"(d[O + 106]), "=f"(d[O + 107]), "=f"(d[O + 108]), "=f"(d[O + 109]), "=f"(d[O + 110]), "=f"(d[O + 111]),
          "=f"(d[O + 112]), "=f"(d[O + 113]), "=f"(d[O + 114]), "=f"(d[O + 115]), "=f"(d[O + 116]), "=f"(d[O + 117]), "=f"(d[O + 118]), "=f"(d[O + 119]),
          "=f"(d[O + 120]), "=f"(d[O + 121]), "=f"(d[O + 122]), "=f"(d[O + 123]), "=f"(d[O + 124]), "=f"(d[O + 125]), "=f"(d[O + 126]), "=f"(d[O + 127])
        : "r"(a0), "r"(a1), "r"(a2), "r"(a3), "l"(db), "l"((uint64_t)(ob >> 4)), "n"(TB));
}
template <int TB, int O, int N>
__device__ __forceinline__ void wgmma_rs256_a(float (&d)[N], uint32_t a0, uint32_t a1, uint32_t a2, uint32_t a3, uint64_t db, int ob) {
    asm volatile("{\n.reg .b64 b;\nadd.u64 b, %132, %133;\n"
        "wgmma.mma_async.sync.aligned.m64n256k16.f32.bf16.bf16 "
        "{%0, %1, %2, %3, %4, %5, %6, %7, %8, %9, %10, %11, %12, %13, %14, %15, "
        "%16, %17, %18, %19, %20, %21, %22, %23, %24, %25, %26, %27, %28, %29, %30, %31, "
        "%32, %33, %34, %35, %36, %37, %38, %39, %40, %41, %42, %43, %44, %45, %46, %47, "
        "%48, %49, %50, %51, %52, %53, %54, %55, %56, %57, %58, %59, %60, %61, %62, %63, "
        "%64, %65, %66, %67, %68, %69, %70, %71, %72, %73, %74, %75, %76, %77, %78, %79, "
        "%80, %81, %82, %83, %84, %85, %86, %87, %88, %89, %90, %91, %92, %93, %94, %95, "
        "%96, %97, %98, %99, %100, %101, %102, %103, %104, %105, %106, %107, %108, %109, %110, %111, "
        "%112, %113, %114, %115, %116, %117, %118, %119, %120, %121, %122, %123, %124, %125, %126, %127}, "
        "{%128, %129, %130, %131}, b, 1, 1, 1, %134;\n}\n"
        : "+f"(d[O + 0]), "+f"(d[O + 1]), "+f"(d[O + 2]), "+f"(d[O + 3]), "+f"(d[O + 4]), "+f"(d[O + 5]), "+f"(d[O + 6]), "+f"(d[O + 7]),
          "+f"(d[O + 8]), "+f"(d[O + 9]), "+f"(d[O + 10]), "+f"(d[O + 11]), "+f"(d[O + 12]), "+f"(d[O + 13]), "+f"(d[O + 14]), "+f"(d[O + 15]),
          "+f"(d[O + 16]), "+f"(d[O + 17]), "+f"(d[O + 18]), "+f"(d[O + 19]), "+f"(d[O + 20]), "+f"(d[O + 21]), "+f"(d[O + 22]), "+f"(d[O + 23]),
          "+f"(d[O + 24]), "+f"(d[O + 25]), "+f"(d[O + 26]), "+f"(d[O + 27]), "+f"(d[O + 28]), "+f"(d[O + 29]), "+f"(d[O + 30]), "+f"(d[O + 31]),
          "+f"(d[O + 32]), "+f"(d[O + 33]), "+f"(d[O + 34]), "+f"(d[O + 35]), "+f"(d[O + 36]), "+f"(d[O + 37]), "+f"(d[O + 38]), "+f"(d[O + 39]),
          "+f"(d[O + 40]), "+f"(d[O + 41]), "+f"(d[O + 42]), "+f"(d[O + 43]), "+f"(d[O + 44]), "+f"(d[O + 45]), "+f"(d[O + 46]), "+f"(d[O + 47]),
          "+f"(d[O + 48]), "+f"(d[O + 49]), "+f"(d[O + 50]), "+f"(d[O + 51]), "+f"(d[O + 52]), "+f"(d[O + 53]), "+f"(d[O + 54]), "+f"(d[O + 55]),
          "+f"(d[O + 56]), "+f"(d[O + 57]), "+f"(d[O + 58]), "+f"(d[O + 59]), "+f"(d[O + 60]), "+f"(d[O + 61]), "+f"(d[O + 62]), "+f"(d[O + 63]),
          "+f"(d[O + 64]), "+f"(d[O + 65]), "+f"(d[O + 66]), "+f"(d[O + 67]), "+f"(d[O + 68]), "+f"(d[O + 69]), "+f"(d[O + 70]), "+f"(d[O + 71]),
          "+f"(d[O + 72]), "+f"(d[O + 73]), "+f"(d[O + 74]), "+f"(d[O + 75]), "+f"(d[O + 76]), "+f"(d[O + 77]), "+f"(d[O + 78]), "+f"(d[O + 79]),
          "+f"(d[O + 80]), "+f"(d[O + 81]), "+f"(d[O + 82]), "+f"(d[O + 83]), "+f"(d[O + 84]), "+f"(d[O + 85]), "+f"(d[O + 86]), "+f"(d[O + 87]),
          "+f"(d[O + 88]), "+f"(d[O + 89]), "+f"(d[O + 90]), "+f"(d[O + 91]), "+f"(d[O + 92]), "+f"(d[O + 93]), "+f"(d[O + 94]), "+f"(d[O + 95]),
          "+f"(d[O + 96]), "+f"(d[O + 97]), "+f"(d[O + 98]), "+f"(d[O + 99]), "+f"(d[O + 100]), "+f"(d[O + 101]), "+f"(d[O + 102]), "+f"(d[O + 103]),
          "+f"(d[O + 104]), "+f"(d[O + 105]), "+f"(d[O + 106]), "+f"(d[O + 107]), "+f"(d[O + 108]), "+f"(d[O + 109]), "+f"(d[O + 110]), "+f"(d[O + 111]),
          "+f"(d[O + 112]), "+f"(d[O + 113]), "+f"(d[O + 114]), "+f"(d[O + 115]), "+f"(d[O + 116]), "+f"(d[O + 117]), "+f"(d[O + 118]), "+f"(d[O + 119]),
          "+f"(d[O + 120]), "+f"(d[O + 121]), "+f"(d[O + 122]), "+f"(d[O + 123]), "+f"(d[O + 124]), "+f"(d[O + 125]), "+f"(d[O + 126]), "+f"(d[O + 127])
        : "r"(a0), "r"(a1), "r"(a2), "r"(a3), "l"(db), "l"((uint64_t)(ob >> 4)), "n"(TB));
}

template <int O, int N>
__device__ __forceinline__ void mma64x4(float (&d)[N], uint32_t a, uint32_t b) {
    asm volatile(
        "{\n.reg .b32 t;\n.reg .b64 a<4>, b<4>;\nadd.u32 t, %32, 0;\nmov.b64 a0, {t, 0x40000040};\nadd.u32 t, %33, 0;\nmov.b64 b0, {t, 0x40000040};\nadd.u32 "
        "t, %32, 2;\nmov.b64 a1, {t, 0x40000040};\nadd.u32 t, %33, 128;\nmov.b64 b1, {t, 0x40000040};\nadd.u32 t, %32, 4;\nmov.b64 a2, {t, "
        "0x40000040};\nadd.u32 t, %33, 256;\nmov.b64 b2, {t, 0x40000040};\nadd.u32 t, %32, 6;\nmov.b64 a3, {t, 0x40000040};\nadd.u32 t, %33, 384;\nmov.b64 b3, "
        "{t, 0x40000040};\n"
        "wgmma.mma_async.sync.aligned.m64n64k16.f32.bf16.bf16 {%0, %1, %2, %3, %4, %5, %6, %7, %8, %9, %10, %11, %12, %13, %14, %15, %16, %17, %18, %19, %20, "
        "%21, %22, %23, %24, %25, %26, %27, %28, %29, %30, %31}, a0, b0, 1, 1, 1, 0, 1;\n"
        "wgmma.mma_async.sync.aligned.m64n64k16.f32.bf16.bf16 {%0, %1, %2, %3, %4, %5, %6, %7, %8, %9, %10, %11, %12, %13, %14, %15, %16, %17, %18, %19, %20, "
        "%21, %22, %23, %24, %25, %26, %27, %28, %29, %30, %31}, a1, b1, 1, 1, 1, 0, 1;\n"
        "wgmma.mma_async.sync.aligned.m64n64k16.f32.bf16.bf16 {%0, %1, %2, %3, %4, %5, %6, %7, %8, %9, %10, %11, %12, %13, %14, %15, %16, %17, %18, %19, %20, "
        "%21, %22, %23, %24, %25, %26, %27, %28, %29, %30, %31}, a2, b2, 1, 1, 1, 0, 1;\n"
        "wgmma.mma_async.sync.aligned.m64n64k16.f32.bf16.bf16 {%0, %1, %2, %3, %4, %5, %6, %7, %8, %9, %10, %11, %12, %13, %14, %15, %16, %17, %18, %19, %20, "
        "%21, %22, %23, %24, %25, %26, %27, %28, %29, %30, %31}, a3, b3, 1, 1, 1, 0, 1;\n"
        "}\n"
        : "+f"(d[O + 0]), "+f"(d[O + 1]), "+f"(d[O + 2]), "+f"(d[O + 3]), "+f"(d[O + 4]), "+f"(d[O + 5]), "+f"(d[O + 6]), "+f"(d[O + 7]),
          "+f"(d[O + 8]), "+f"(d[O + 9]), "+f"(d[O + 10]), "+f"(d[O + 11]), "+f"(d[O + 12]), "+f"(d[O + 13]), "+f"(d[O + 14]), "+f"(d[O + 15]),
          "+f"(d[O + 16]), "+f"(d[O + 17]), "+f"(d[O + 18]), "+f"(d[O + 19]), "+f"(d[O + 20]), "+f"(d[O + 21]), "+f"(d[O + 22]), "+f"(d[O + 23]),
          "+f"(d[O + 24]), "+f"(d[O + 25]), "+f"(d[O + 26]), "+f"(d[O + 27]), "+f"(d[O + 28]), "+f"(d[O + 29]), "+f"(d[O + 30]), "+f"(d[O + 31])
        : "r"(a), "r"(b));
}

template <int O, int H, int N>
__device__ __forceinline__ void mma64rs4(float (&d)[N], const uint32_t (&h)[44], uint32_t b) {
    asm volatile(
        "{\n.reg .b32 t;\n.reg .b64 b<4>;\nadd.u32 t, %32, 0;\nmov.b64 b0, {t, 0x40000040};\nadd.u32 t, %32, 128;\nmov.b64 b1, {t, 0x40000040};\nadd.u32 t, "
        "%32, 256;\nmov.b64 b2, {t, 0x40000040};\nadd.u32 t, %32, 384;\nmov.b64 b3, {t, 0x40000040};\n"
        "wgmma.mma_async.sync.aligned.m64n64k16.f32.bf16.bf16 {%0, %1, %2, %3, %4, %5, %6, %7, %8, %9, %10, %11, %12, %13, %14, %15, %16, %17, %18, %19, %20, "
        "%21, %22, %23, %24, %25, %26, %27, %28, %29, %30, %31}, {%33, %34, %35, %36}, b0, 1, 1, 1, 1;\n"
        "wgmma.mma_async.sync.aligned.m64n64k16.f32.bf16.bf16 {%0, %1, %2, %3, %4, %5, %6, %7, %8, %9, %10, %11, %12, %13, %14, %15, %16, %17, %18, %19, %20, "
        "%21, %22, %23, %24, %25, %26, %27, %28, %29, %30, %31}, {%37, %38, %39, %40}, b1, 1, 1, 1, 1;\n"
        "wgmma.mma_async.sync.aligned.m64n64k16.f32.bf16.bf16 {%0, %1, %2, %3, %4, %5, %6, %7, %8, %9, %10, %11, %12, %13, %14, %15, %16, %17, %18, %19, %20, "
        "%21, %22, %23, %24, %25, %26, %27, %28, %29, %30, %31}, {%41, %42, %43, %44}, b2, 1, 1, 1, 1;\n"
        "wgmma.mma_async.sync.aligned.m64n64k16.f32.bf16.bf16 {%0, %1, %2, %3, %4, %5, %6, %7, %8, %9, %10, %11, %12, %13, %14, %15, %16, %17, %18, %19, %20, "
        "%21, %22, %23, %24, %25, %26, %27, %28, %29, %30, %31}, {%45, %46, %47, %48}, b3, 1, 1, 1, 1;\n"
        "}\n"
        : "+f"(d[O + 0]), "+f"(d[O + 1]), "+f"(d[O + 2]), "+f"(d[O + 3]), "+f"(d[O + 4]), "+f"(d[O + 5]), "+f"(d[O + 6]), "+f"(d[O + 7]),
          "+f"(d[O + 8]), "+f"(d[O + 9]), "+f"(d[O + 10]), "+f"(d[O + 11]), "+f"(d[O + 12]), "+f"(d[O + 13]), "+f"(d[O + 14]), "+f"(d[O + 15]),
          "+f"(d[O + 16]), "+f"(d[O + 17]), "+f"(d[O + 18]), "+f"(d[O + 19]), "+f"(d[O + 20]), "+f"(d[O + 21]), "+f"(d[O + 22]), "+f"(d[O + 23]),
          "+f"(d[O + 24]), "+f"(d[O + 25]), "+f"(d[O + 26]), "+f"(d[O + 27]), "+f"(d[O + 28]), "+f"(d[O + 29]), "+f"(d[O + 30]), "+f"(d[O + 31])
        : "r"(b), "r"(h[H + 0]), "r"(h[H + 1]), "r"(h[H + 2]), "r"(h[H + 3]), "r"(h[H + 4]), "r"(h[H + 5]), "r"(h[H + 6]), "r"(h[H + 7]), "r"(h[H + 8]), "r"(h[H + 9]), "r"(h[H + 10]), "r"(h[H + 11]), "r"(h[H + 12]), "r"(h[H + 13]), "r"(h[H + 14]), "r"(h[H + 15]));
}
template <int O, int H, int N>
__device__ __forceinline__ void mma64rs3(float (&d)[N], const uint32_t (&h)[44], uint32_t b) {
    asm volatile(
        "{\n.reg .b32 t;\n.reg .b64 b<4>;\nadd.u32 t, %32, 0;\nmov.b64 b0, {t, 0x40000040};\nadd.u32 t, %32, 128;\nmov.b64 b1, {t, 0x40000040};\nadd.u32 t, "
        "%32, 256;\nmov.b64 b2, {t, 0x40000040};\n"
        "wgmma.mma_async.sync.aligned.m64n64k16.f32.bf16.bf16 {%0, %1, %2, %3, %4, %5, %6, %7, %8, %9, %10, %11, %12, %13, %14, %15, %16, %17, %18, %19, %20, "
        "%21, %22, %23, %24, %25, %26, %27, %28, %29, %30, %31}, {%33, %34, %35, %36}, b0, 1, 1, 1, 1;\n"
        "wgmma.mma_async.sync.aligned.m64n64k16.f32.bf16.bf16 {%0, %1, %2, %3, %4, %5, %6, %7, %8, %9, %10, %11, %12, %13, %14, %15, %16, %17, %18, %19, %20, "
        "%21, %22, %23, %24, %25, %26, %27, %28, %29, %30, %31}, {%37, %38, %39, %40}, b1, 1, 1, 1, 1;\n"
        "wgmma.mma_async.sync.aligned.m64n64k16.f32.bf16.bf16 {%0, %1, %2, %3, %4, %5, %6, %7, %8, %9, %10, %11, %12, %13, %14, %15, %16, %17, %18, %19, %20, "
        "%21, %22, %23, %24, %25, %26, %27, %28, %29, %30, %31}, {%41, %42, %43, %44}, b2, 1, 1, 1, 1;\n"
        "}\n"
        : "+f"(d[O + 0]), "+f"(d[O + 1]), "+f"(d[O + 2]), "+f"(d[O + 3]), "+f"(d[O + 4]), "+f"(d[O + 5]), "+f"(d[O + 6]), "+f"(d[O + 7]),
          "+f"(d[O + 8]), "+f"(d[O + 9]), "+f"(d[O + 10]), "+f"(d[O + 11]), "+f"(d[O + 12]), "+f"(d[O + 13]), "+f"(d[O + 14]), "+f"(d[O + 15]),
          "+f"(d[O + 16]), "+f"(d[O + 17]), "+f"(d[O + 18]), "+f"(d[O + 19]), "+f"(d[O + 20]), "+f"(d[O + 21]), "+f"(d[O + 22]), "+f"(d[O + 23]),
          "+f"(d[O + 24]), "+f"(d[O + 25]), "+f"(d[O + 26]), "+f"(d[O + 27]), "+f"(d[O + 28]), "+f"(d[O + 29]), "+f"(d[O + 30]), "+f"(d[O + 31])
        : "r"(b), "r"(h[H + 0]), "r"(h[H + 1]), "r"(h[H + 2]), "r"(h[H + 3]), "r"(h[H + 4]), "r"(h[H + 5]), "r"(h[H + 6]), "r"(h[H + 7]), "r"(h[H + 8]), "r"(h[H + 9]), "r"(h[H + 10]), "r"(h[H + 11]));
}


struct Params {
    CUtensorMap x, wr, wi, w1, cr, ci, w2, out;
};

template <int O>
__device__ __forceinline__ void stage_out(float (&acc)[128], float g0, float g1, uint32_t row_addr, uint32_t shi, uint32_t sx7) {
    reg_pin<O, O + 32>(acc);
#pragma unroll
    for (int t = 0; t < 4; t++) {
        const int b = O + 8 * t;
        stsm4(row_addr + (((2 * t + shi) ^ sx7) << 4), pack_bf16(acc[b + 0] * g0, acc[b + 1] * g0), pack_bf16(acc[b + 2] * g1, acc[b + 3] * g1),
              pack_bf16(acc[b + 4] * g0, acc[b + 5] * g0), pack_bf16(acc[b + 6] * g1, acc[b + 7] * g1));
    }
    fence_proxy_async_smem();
}
template <int POS>
__device__ __forceinline__ void pass_block(float (&acc)[128], const uint32_t (&hp)[44], int it, uint32_t da, uint32_t db) {
    if (it < 2) mma64x4<32 * POS>(acc, da, db);
    if (it == 2) mma64rs4<32 * POS, 0>(acc, hp, db);
    if (it == 3) mma64rs4<32 * POS, 16>(acc, hp, db);
    if (it == 4) mma64rs3<32 * POS, 32>(acc, hp, db);
}
__device__ __forceinline__ void rebind(float (&acc)[128]) {
#pragma unroll
    for (int i = 0; i < 128; i++) { float t; asm volatile("mov.b32 %0, %1;" : "=f"(t) : "f"(acc[i]) : "memory"); acc[i] = t; }
}

__global__ void __cluster_dims__(2, 1, 1) __launch_bounds__(384, 1)
fused_kernel(const __grid_constant__ Params P, const __nv_bfloat16* __restrict__ gate_w, __nv_bfloat16* __restrict__ out,
             const unsigned char* __restrict__ w2) {
    extern __shared__ __align__(1024) unsigned char smem_raw[];
    const uint32_t sm = (s2u(smem_raw) + 1023u) & ~1023u;
    const uint32_t bar = sm + OFF_BAR;
    float* sgate = reinterpret_cast<float*>(smem_raw + (sm - s2u(smem_raw)) + OFF_G);
#define BAR(i) (bar + 8 * (i))

    const int bid = blockIdx.x;
    const int rank = bid & 1;
    const int m = ((bid >> 4) << 1) | rank;
    const int c = (bid >> 1) & 7;
    const int nh = c & 1, j = c >> 1;
    const int warp = __shfl_sync(0xffffffffu, threadIdx.x >> 5, 0), lane = threadIdx.x & 31;
    const CUtensorMap* const wm = (c < 4) ? &P.wr : &P.wi;
    const long long t_start = clock64();

    if (warp >= 8 && lane == 0) {
        if (warp == 8) {
            mbar_init(BAR(B_FA1), 1);
            fence_proxy_async_smem();
            mbar_expect(BAR(B_FA1), 2 * XS);
            tma2d(sm, &P.x, 0, m * 128, BAR(B_FA1));
            tma2d(sm + OFF_V + nib(W_UNIT, 0) * 8192, wm, 0, (c & 3) * 128, BAR(B_FA1));
            tma2d(sm + OFF_V + (nib(W_UNIT, 0) + 1) * 8192, wm, 0, (c & 3) * 128 + 64, BAR(B_FA1));
        } else if (warp == 9) {
            prefetch_map(&P.w1);
#pragma unroll
            for (int i = B_FA1 + 1; i < B_FX; i++) mbar_init(BAR(i), i < B_DONE ? 1 : 16);
        } else if (warp == 10) {
#pragma unroll
            for (int i = B_FX; i < B_G; i++) mbar_init(BAR(i), i < B_EX ? 1 : i < B_FB ? 8 : i < B_EB ? 1 : i < B_FLAGA ? 16 : i == B_FLAGA + 7 ? 2 : 1);
        } else {
#pragma unroll
            for (int i = B_G; i < NBAR; i++) mbar_init(BAR(i), i >= B_HF ? 1 : i >= B_H ? 8 : i >= B_AB ? 4 : i == B_PART ? 3 : i == B_STAB ? 2 : 1);
            prefetch_map(j < 2 ? &P.cr : &P.ci); prefetch_map(&P.w2); prefetch_map(&P.out);
        }
        asm volatile("fence.mbarrier_init.release.cluster;" ::: "memory");
    }
    __syncwarp();
    asm volatile("barrier.cluster.arrive.relaxed.aligned;\nbarrier.cluster.wait.aligned;" ::: "memory");

    if (warp >= 8) {
        asm volatile("setmaxnreg.dec.sync.aligned.u32 %0;" ::"n"(REG_P));
        const unsigned tag = g_epoch[bid * 32] + 1u;
        if (warp == 8) {
            if (lane == 0) {
#pragma unroll 1
                for (int st = 1; st < 16; st++) {
                    const int k = stepK(st);
                    if (st >= 3 && st < 10) { while (clock64() < t_start + PACE0 + (st - 3) * PACE) {} }
                    if (stepIsA(st)) {
                        if (k == XL_K) mbar_wait(BAR(B_DONE + XL_PRE), 0);
                        mbar_expect(BAR(B_FA1 + k), 2 * XS);
                        tma2d(sm + k * XS, &P.x, k * 64, m * 128, BAR(B_FA1 + k));
                        if (nib(W_PRE, k) != 15) mbar_wait(BAR(B_DONE + nib(W_PRE, k)), 0);
                        tma2d_mc(sm + OFF_V + (nib(W_UNIT, k) + rank) * 8192, wm, k * 64, (c & 3) * 128 + rank * 64, BAR(B_FA1 + k));
                    } else {
                        if (nib(V_PRE, k) != 15) mbar_wait(BAR(B_DONE + nib(V_PRE, k)), 0);
                        mbar_expect(BAR(B_FV + k), VS);
                        for (int nb = 0; nb < 3; nb++)
                            tma2d_mc(sm + OFF_V + (nib(V_UNIT, k) + nb) * 8192 + rank * 4096, &P.w1, c * 176 + nb * 64, k * 64 + rank * 32, BAR(B_FV + k));
                    }
                }
#pragma unroll 1
                for (int i = 0; i < 26; i++) {
                    const int s = slotB(i);
                    const uint32_t dst = sm + s * BS, fb = BAR(B_FB + s);
                    if (i >= 3 && i < 18 && (i & 1)) { mbar_wait(BAR(B_FLAGA + ((i - 3) >> 1)), 0); fence_proxy_async_global(); }
                    if (i == 2) mbar_wait(BAR(B_STAB), 0);
                    else if (i < 4) mbar_wait(BAR(B_DONE + 9 + 2 * s), 0);
                    else mbar_wait(BAR(B_EB + s), nthB(i) ^ 1);
                    if (i >= 22) continue;
                    mbar_expect(fb, BS);
#pragma unroll
                    for (int q = 0; q < 2; q++) {
                        const int e = rank * 2 + q;
                        if (i < 3) {
                            tma2d_mc(dst + ((e - j) & 3) * 8192, &P.w2, nh * 256 + e * 64, c * 176 + i * 64, fb);
                        } else if (i < 17) {
                            bulk_load_mc(dst + ((e - j) & 3) * 8192, g_ab + (size_t)((j * 16 + i - 3) * 8 + nh * 4 + e) * 8192, 8192, fb);
                        } else {
                            const int n = (i - 17) * 4 + e, pass = n / 5, b = passItem(pass, n - 5 * pass), cb = nh * 4 + ((pass + j) & 3);
                            if (b < 2) bulk_load_mc(dst + e * 8192, g_ab + (size_t)((j * 16 + 14 + b) * 8 + cb) * 8192, 8192, fb);
                            else tma2d_mc(dst + e * 8192, &P.w2, cb * 64, (c ^ 1) * 176 + (b - 2) * 64, fb);
                        }
                    }
                    if (i >= 3 && i < 6) mbar_arrive(BAR(B_ISS + i - 3));
                }
            }
        } else if (warp == 10) {
            {
                const uint4* gw = reinterpret_cast<const uint4*>(gate_w) + (lane & 7);
                float s4[4] = {0.f, 0.f, 0.f, 0.f};
                uint4 wa[8];
#pragma unroll
                for (int k = 0; k < 8; k++) wa[k] = __ldg(gw + k * 8);
#pragma unroll
                for (int k = 0; k < 8; k++) {
#pragma unroll
                    for (int i = 0; i < 4; i++)
                        *reinterpret_cast<uint4*>(out + (size_t)(m * 128 + k * 16 + i * 4 + (lane >> 3)) * D_ + nh * 256 + j * 64 + (lane & 7) * 8) = make_uint4(0, 0, 0, 0);
                    mbar_wait(BAR(B_FA1 + k), 0);
#pragma unroll
                    for (int i = 0; i < 4; i++) {
                        const int r = c * 16 + i * 4 + (lane >> 3);
                        uint32_t xv[4];
                        asm volatile("ld.shared.v4.u32 {%0,%1,%2,%3}, [%4];" : "=r"(xv[0]), "=r"(xv[1]), "=r"(xv[2]), "=r"(xv[3])
                                     : "r"(sm + k * XS + r * 128 + (((lane & 7) ^ (r & 7)) << 4)) : "memory");
                        const uint32_t wv[4] = {wa[k].x, wa[k].y, wa[k].z, wa[k].w};
#pragma unroll
                        for (int e = 0; e < 4; e++) {
                            uint32_t pr;
                            asm("mul.rn.bf16x2 %0, %1, %2;" : "=r"(pr) : "r"(xv[e]), "r"(wv[e]));
                            s4[i] += bf_lo(pr);
                            s4[i] += bf_hi(pr);
                        }
                    }
                }
                __syncwarp();
                if (lane == 0) mbar_arrive(BAR(B_GD));
#pragma unroll
                for (int i = 0; i < 4; i++) {
#pragma unroll
                    for (int o = 1; o < 8; o <<= 1) s4[i] += __shfl_xor_sync(0xffffffffu, s4[i], o);
                }
                if ((lane & 7) < 4) {
                    const int i = lane & 3;
                    const float z = bf16r(i == 0 ? s4[0] : i == 1 ? s4[1] : i == 2 ? s4[2] : s4[3]);
                    const float g = bf16r(1.f / (1.f + __expf(-z)));
                    asm volatile("{\n.reg .b64 t;\nmov.b64 t, {%1, %2};\nst.relaxed.gpu.global.b64 [%0], t;\n}"
                                 ::"l"(g_gate + m * 128 + c * 16 + i * 4 + (lane >> 3)), "r"(__float_as_uint(g)), "r"(tag) : "memory");
                }
            }
            __syncwarp();
            if (lane == 0) {
                mbar_wait(BAR(B_AB), 0);
                sleep_until(clock64() + ((m & 7) >> 1) * STAG);
#pragma unroll 1
                for (int i = 0; i < 4; i++) {
                    if (i == 2) mbar_wait(BAR(B_AB + 1), 0);
                    bulk_store(g_ab + (size_t)(((c >> 2) * 32 + m * 2 + (i >> 1)) * 8 + (c & 3) * 2 + (i & 1)) * 8192,
                               sm + (i & 1) * XS + (i >> 1) * 8192, 8192);
                }
                bulk_commit();
                bulk_wait_read();
                if ((m & 7) >= STABG) { mbar_arrive_cta(BAR(B_STAB), 0); mbar_arrive_cta(BAR(B_STAB), 1); }
                bulk_wait_all();
                publish(&g_flagAB[(m * 8 + c) * 32], tag);
                mbar_arrive(BAR(B_PUB));
                if ((m & 7) < STABG) { mbar_arrive_cta(BAR(B_STAB), 0); mbar_arrive_cta(BAR(B_STAB), 1); }
                unsigned char* hb = g_h + (size_t)bid * 3 * XS;
#pragma unroll 1
                for (int t = 0; t < 3; t++) {
                    mbar_wait(BAR(B_H + t), 0);
#pragma unroll 1
                    for (int off = 0; off < XS; off += H_CH) {
                        bulk_store(hb + t * XS + off, sm + OFF_X + XS + off, H_CH);
                        bulk_commit();
                        bulk_wait_read();
                    }
                    mbar_arrive(BAR(B_HF + t));
                }
                bulk_wait_all();
                publish(&g_flagH[bid * 32], tag);
                g_epoch[bid * 32] = tag;
                mbar_wait(BAR(B_PART), 0);
                fence_proxy_async_global();
#pragma unroll 1
                for (int p = 0; p < 6; p++) {
                    mbar_wait(BAR(B_SND + p), 0);
                    tma2d_red(&P.out, (nh * 4 + (((p >> 1) + j) & 3)) * 64, m * 128 + (p & 1) * 64, sm + stageOff(p >> 1) + (p & 1) * 8192);
                    bulk_commit();
                }
                bulk_wait_read();
            }
        } else if (warp == 9) {
            mbar_wait(BAR(B_GD), 0);
            uint4 u0, u1;
            unsigned n = 0;
            do {
                u0 = ld_b128(g_gate + m * 128 + lane * 4);
                u1 = ld_b128(g_gate + m * 128 + lane * 4 + 2);
            } while (!(u0.y == tag && u0.w == tag && u1.y == tag && u1.w == tag) && ++n < SPIN_LIMIT);
            reinterpret_cast<uint4*>(sgate)[lane] = make_uint4(u0.x, u0.z, u1.x, u1.z);
            __syncwarp();
            if (lane == 0) mbar_arrive(BAR(B_G));
            const unsigned* fp = (lane < 16) ? &g_flagAB[(((j & 1) * 8 + (lane & 7)) * 8 + (j >> 1) * 4 + nh * 2 + (rank ^ (lane >> 3))) * 32]
                                 : (lane == 16) ? &g_flagH[(bid ^ 2) * 32] : &g_flagAB[(m * 8 + ((j + lane) & 3) * 2 + nh) * 32];
            bool done = lane >= 20 || (lane >= 8 && lane < 15);
            n = 0;
            do {
                if (!done && ld_acquire(fp) == tag) {
                    mbar_arrive(lane < 16 ? BAR(B_FLAGA + (lane & 7)) : lane == 16 ? BAR(B_FLAGH) : BAR(B_PART));
                    done = true;
                }
            } while (!__all_sync(0xffffffffu, done) && ++n < SPIN_LIMIT);
        } else {
            sleep_until(t_start + PFW_START);
#pragma unroll
            for (int i = 0; i < 3; i++)
                if (i * 32 + lane < 86) asm volatile("prefetch.global.L2 [%0];" ::"l"(w2 + bid * 11008 + (i * 32 + lane) * 128));
            if (lane == 0) {
                const CUtensorMap* cm = (j < 2) ? &P.cr : &P.ci;
                if ((m & 7) < PUBG) mbar_wait(BAR(B_PUB), 0);
#pragma unroll 1
                for (int i = 0; i < 19; i++) {
                    const int sx = slotX(i);
                    if (i < 5) mbar_wait(BAR(B_DONE + nib(X_PRE, i)), 0);
                    else if (i != 16) mbar_wait(BAR(B_EX + sx), nthX(i) ^ 1);
                    else mbar_wait(BAR(B_HF + 2), 0);
                    if (i >= A_LEAD && i < 5) mbar_wait(BAR(B_ISS + (i - A_LEAD + 1 > 2 ? 2 : i - A_LEAD + 1)), 0);
                    if (i == 16) { mbar_wait(BAR(B_FLAGH), 0); fence_proxy_async_global(); }
                    mbar_expect(BAR(B_FX + sx), XS);
                    if (i < 16) tma2d(sm + OFF_X + sx * XS, cm, (j & 1) * 1024 + i * 64, m * 128, BAR(B_FX + sx));
                    else bulk_load(sm + OFF_X + sx * XS, g_h + (size_t)((bid ^ 2) * 3 + i - 16) * XS, XS, BAR(B_FX + sx));
                }
            }
        }
    } else {
        asm volatile("setmaxnreg.inc.sync.aligned.u32 %0;" ::"n"(REG_C));
        const int wg = warp >> 2;
        const int rloc = wg * 64 + (warp & 3) * 16 + (lane >> 2);
        const uint64_t dK = mk_desc(sm, 16, 1024);
        const uint64_t dN = mk_desc(sm, 8192, 1024);
        const uint64_t dA = dK + ((wg * 8192) >> 4);
        const int srow = wg * 64 + (warp & 3) * 16 + ((lane >> 3) & 1) * 8 + (lane & 7);
        const uint32_t saddr = sm + srow * 128, sx7 = lane & 7, shi = lane >> 4;

        float acc[128];
        uint32_t hp[44];
        float g0, g1;
        {
            float ab[64], hh[88];
#pragma unroll
            for (int st = 0; st < 16; st++) {
                const int kx = stepK(st);
                if (stepIsA(st)) {
                    mbar_wait(BAR(B_FA1 + kx), 0);
                    wg_fence();
#pragma unroll
                    for (int k = 0; k < 4; k++) {
                        if ((st | k) == 0) wgmma_n128_z<0, 0>(ab, dA, 0, dK, OFF_V + nib(W_UNIT, 0) * 8192);
                        else wgmma_n128_a<0, 0>(ab, dA, kx * XS + k * 32, dK, OFF_V + nib(W_UNIT, kx) * 8192 + k * 32);
                    }
                } else {
                    mbar_wait(BAR(B_FV + kx), 0);
                    wg_fence();
#pragma unroll
                    for (int k = 0; k < 4; k++) {
                        if ((kx | k) == 0) wgmma_n176_z<1, 0>(hh, dA, 0, dN, OFF_V + nib(V_UNIT, 0) * 8192);
                        else wgmma_n176_a<1, 0>(hh, dA, kx * XS + k * 32, dN, OFF_V + nib(V_UNIT, kx) * 8192 + k * 2048);
                    }
                }
                wg_commit();
                if (st > 0) {
                    wg_wait<1>();
                    if (lane < 2) mbar_arrive_cta(BAR(B_DONE + st - 1), lane);
                }
                if (st == AB_STEP) {
                    reg_pin<0, 64>(ab);
                    mbar_wait(BAR(B_GD), 0);
                    const uint32_t neg = (c < 4) ? 0u : 0x80008000u;
#pragma unroll
                    for (int t = 0; t < 8; t++)
                        stsm4(saddr + (t >> 2) * XS + (((2 * (t & 3) + shi) ^ sx7) << 4), pack_bf16(ab[8 * t], ab[8 * t + 1]) ^ neg,
                              pack_bf16(ab[8 * t + 2], ab[8 * t + 3]) ^ neg, pack_bf16(ab[8 * t + 4], ab[8 * t + 5]) ^ neg,
                              pack_bf16(ab[8 * t + 6], ab[8 * t + 7]) ^ neg);
                    fence_proxy_async_smem();
                    __syncwarp();
                    if (lane == 0) mbar_arrive(BAR(B_AB + wg));
                }
            }
            mbar_wait(BAR(B_G), 0);
            g0 = sgate[rloc]; g1 = sgate[rloc + 8];
            const float o0 = bf16r(1.f - g0), o1 = bf16r(1.f - g1);
            g0 = fmaxf(g0, 1e-9f); g1 = fmaxf(g1, 1e-9f);
            const float s0 = __fdividef(o0, g0), s1 = __fdividef(o1, g1);
            wg_wait<0>();
            reg_pin<0, 88>(hh);
            if (lane < 2) mbar_arrive_cta(BAR(B_DONE + 15), lane);
#pragma unroll
            for (int i = 0; i < 22; i++) {
                hp[2 * i + 0] = pack_bf16_relu(hh[4 * i + 0] * s0, hh[4 * i + 1] * s0);
                hp[2 * i + 1] = pack_bf16_relu(hh[4 * i + 2] * s1, hh[4 * i + 3] * s1);
            }
        }
#pragma unroll
        for (int u = 0; u < 3; u++) {
            mbar_wait(BAR(B_FB + slotB(u)), 0);
            wg_fence();
#pragma unroll
            for (int k = 0; k < 4; k++) {
                const int t = 4 * u + k;
                if (t == 0) wgmma_rs256_z<1, 0>(acc, hp[0], hp[1], hp[2], hp[3], dN, slotB(0) * BS);
                else if (t < 11) wgmma_rs256_a<1, 0>(acc, hp[4 * t], hp[4 * t + 1], hp[4 * t + 2], hp[4 * t + 3], dN, slotB(u) * BS + k * 2048);
            }
            wg_commit();
            if (u > 0) {
                wg_wait<1>();
                if (lane < 2) mbar_arrive_cta(BAR(B_EB + slotB(u - 1)), lane);
            }
        }
#pragma unroll
        for (int kb = 0; kb < 14; kb++) {
            mbar_wait(BAR(B_FX + slotX(kb)), nthX(kb));
            mbar_wait(BAR(B_FB + slotB(kb + 3)), nthB(kb + 3));
            wg_fence();
#pragma unroll
            for (int k = 0; k < 4; k++)
                wgmma_n256_a<1, 0>(acc, dA, OFF_X + slotX(kb) * XS + k * 32, dN, slotB(kb + 3) * BS + k * 2048);
            wg_commit();
            wg_wait<1>();
            if (lane < 2) mbar_arrive_cta(BAR(B_EB + slotB(kb + 2)), lane);
            if (lane == 0 && kb > 0) mbar_arrive(BAR(B_EX + slotX(kb - 1)));
            if (kb >= HS0 && (kb - HS0) % HSS == 0 && (kb - HS0) / HSS < 3) {
                const int pc = (kb - HS0) / HSS;
                mbar_wait(pc == 0 ? BAR(B_DONE + 15) : BAR(B_HF + pc - 1), 0);
#pragma unroll
                for (int t = 4 * pc; t < 4 * pc + 4 && t < 11; t++)
                    stsm4(saddr + OFF_X + XS + (((2 * (t & 3) + shi) ^ sx7) << 4), hp[4 * t], hp[4 * t + 1], hp[4 * t + 2], hp[4 * t + 3]);
                fence_proxy_async_smem();
                __syncwarp();
                if (lane == 0) mbar_arrive(BAR(B_H + pc));
            }
        }
        wg_wait<0>();
        rebind(acc);
        if (lane < 2) mbar_arrive_cta(BAR(B_EB + slotB(16)), lane);
#pragma unroll
        for (int n = 0; n < 20; n++) {
            const int pass = n / 5, b = n % 5, u = 17 + (n >> 2);
            if (!(n & 3)) mbar_wait(BAR(B_FB + slotB(u)), nthB(u));
            if (n < 2) mbar_wait(BAR(B_FX + slotX(14 + b)), nthX(14 + b));
            if (n == 18 && wg == 1) bar_sync(3, 256);
            wg_fence();
            const int it = passItem(pass, b);
            const uint32_t da = (uint32_t)dA + ((OFF_X + slotX(14 + (it & 1)) * XS) >> 4), db = (uint32_t)dN + ((slotB(u) * BS + (n & 3) * 8192) >> 4);
            if (pass == 0) pass_block<0>(acc, hp, it, da, db);
            if (pass == 1) pass_block<1>(acc, hp, it, da, db);
            if (pass == 2) pass_block<2>(acc, hp, it, da, db);
            if (pass == 3) pass_block<3>(acc, hp, it, da, db);
            wg_commit();
            if (n >= 1 && n <= 3) {
                mbar_wait(BAR(B_FX + slotX(15 + n)), nthX(15 + n));
#pragma unroll
                for (int t = 4 * (n - 1); t < 4 * n && t < 11; t++)
                    ldsm4(saddr + OFF_X + slotX(15 + n) * XS + (((2 * (t & 3) + shi) ^ sx7) << 4), hp[4 * t], hp[4 * t + 1], hp[4 * t + 2], hp[4 * t + 3]);
            }
            if (pass >= 1 && b == 1) {
                if (pass == 1) stage_out<0>(acc, g0, g1, saddr + stageOff(0), shi, sx7);
                if (pass == 2) stage_out<32>(acc, g0, g1, saddr + stageOff(1), shi, sx7);
                if (pass == 3) stage_out<64>(acc, g0, g1, saddr + stageOff(2), shi, sx7);
                __syncwarp();
                if (lane == 0) mbar_arrive(BAR(B_SND + 2 * (pass - 1) + wg));
            }
            if (n == 19 && wg == 0) asm volatile("bar.arrive 3, 256;" ::: "memory");
            if (n > 0 && n <= 16) wg_wait<1>();
            if (n > 0 && !(n & 3) && lane < 2) mbar_arrive_cta(BAR(B_EB + slotB(u - 1)), lane);
        }
        mbar_wait(BAR(B_PART), 0);
        wg_wait<0>();
        stage_out<96>(acc, g0, g1, saddr + stageOff(3), shi, sx7);
        bar_sync(1 + wg, 128);
        if ((threadIdx.x & 127) == 0) {
            fence_proxy_async_global();
            tma2d_red(&P.out, (nh * 4 + ((3 + j) & 3)) * 64, m * 128 + wg * 64, sm + stageOff(3) + wg * 8192);
            bulk_commit();
        }
        if (lane < 2) mbar_arrive_cta(BAR(B_EB + slotB(21)), lane);
        if ((threadIdx.x & 127) == 0) bulk_wait_read();
    }
#undef BAR
}

__global__ void fb_stage1(const __nv_bfloat16* x, const __nv_bfloat16* wr, const __nv_bfloat16* wi, const __nv_bfloat16* w1) {
    const int t = blockIdx.y, n = blockIdx.x * blockDim.x + threadIdx.x;
    if (n >= 2 * D_ + F_) return;
    float s = 0.f;
    for (int k = 0; k < D_; k++)
        s += __bfloat162float(x[t * D_ + k]) *
             __bfloat162float(n < D_ ? wr[n * D_ + k] : n < 2 * D_ ? wi[(n - D_) * D_ + k] : w1[k * F_ + n - 2 * D_]);
    if (n < 2 * D_) reinterpret_cast<__nv_bfloat16*>(g_ab)[((n >> 9) * S_ + t) * D_ + (n & 511)] = __float2bfloat16_rn(s);
    else reinterpret_cast<__nv_bfloat16*>(g_h)[t * F_ + n - 2 * D_] = __float2bfloat16_rn(fmaxf(s, 0.f));
}
__global__ void fb_stage2(const __nv_bfloat16* x, const __nv_bfloat16* cr, const __nv_bfloat16* ci, const __nv_bfloat16* w2,
                          const __nv_bfloat16* gw, __nv_bfloat16* out) {
    const int t = blockIdx.x, e = threadIdx.x;
    const __nv_bfloat16 *ab = reinterpret_cast<const __nv_bfloat16*>(g_ab), *h = reinterpret_cast<const __nv_bfloat16*>(g_h);
    float z = 0.f, y = 0.f, f = 0.f;
    for (int k = 0; k < D_; k++) z += bf16r(__bfloat162float(x[t * D_ + k]) * __bfloat162float(gw[k]));
    for (int k = 0; k < S_; k++)
        y += __bfloat162float(cr[t * S_ + k]) * __bfloat162float(ab[k * D_ + e]) - __bfloat162float(ci[t * S_ + k]) * __bfloat162float(ab[(S_ + k) * D_ + e]);
    for (int k = 0; k < F_; k++) f += __bfloat162float(h[t * F_ + k]) * __bfloat162float(w2[k * D_ + e]);
    const float g = bf16r(1.f / (1.f + expf(-bf16r(z))));
    out[t * D_ + e] = __float2bfloat16_rn(g * y + bf16r(1.f - g) * f);
}

typedef CUresult (*EncodeFn)(CUtensorMap*, CUtensorMapDataType, cuuint32_t, void*, const cuuint64_t*, const cuuint64_t*,
                             const cuuint32_t*, const cuuint32_t*, CUtensorMapInterleave, CUtensorMapSwizzle,
                             CUtensorMapL2promotion, CUtensorMapFloatOOBfill);

void enc2d(EncodeFn f, CUtensorMap* m, const void* p, int rows, int cols, int brows) {
    cuuint64_t gd[2] = {(cuuint64_t)cols, (cuuint64_t)rows};
    cuuint64_t gs[1] = {(cuuint64_t)cols * 2};
    cuuint32_t bd[2] = {64, (cuuint32_t)brows};
    cuuint32_t es[2] = {1, 1};
    f(m, CU_TENSOR_MAP_DATA_TYPE_BFLOAT16, 2, const_cast<void*>(p), gd, gs, bd, es, CU_TENSOR_MAP_INTERLEAVE_NONE,
      CU_TENSOR_MAP_SWIZZLE_128B, CU_TENSOR_MAP_L2_PROMOTION_L2_128B, CU_TENSOR_MAP_FLOAT_OOB_FILL_NONE);
}

}

extern "C" void kernel_launch(void* const* d_in, const int* in_sizes, int n_in, void* d_out, int out_size) {
    (void)in_sizes; (void)n_in; (void)out_size;
    typedef const __nv_bfloat16* cbf;
    static EncodeFn enc = nullptr;
    static bool fits = true, ready = false;
    if (!ready) {
        ready = true;
        void* fn = nullptr;
        cudaDriverEntryPointQueryResult qr;
        cudaGetDriverEntryPoint("cuTensorMapEncodeTiled", &fn, cudaEnableDefault, &qr);
        enc = (EncodeFn)fn;
        cudaFuncSetAttribute(fused_kernel, cudaFuncAttributeMaxDynamicSharedMemorySize, SMEM_BYTES);
        cudaLaunchConfig_t cfg = {};
        cfg.gridDim = dim3(128); cfg.blockDim = dim3(384); cfg.dynamicSmemBytes = SMEM_BYTES;
        cudaLaunchAttribute at;
        at.id = cudaLaunchAttributeClusterDimension; at.val.clusterDim.x = 2; at.val.clusterDim.y = 1; at.val.clusterDim.z = 1;
        cfg.attrs = &at; cfg.numAttrs = 1;
        int ncl = 0;
        if (cudaOccupancyMaxActiveClusters(&ncl, fused_kernel, &cfg) == cudaSuccess) fits = ncl >= 64;
        (void)cudaGetLastError();
    }
    if (!fits || !enc) {
        fb_stage1<<<dim3((2 * D_ + F_ + 255) / 256, S_), 256>>>((cbf)d_in[0], (cbf)d_in[3], (cbf)d_in[4], (cbf)d_in[6]);
        fb_stage2<<<S_, D_>>>((cbf)d_in[0], (cbf)d_in[1], (cbf)d_in[2], (cbf)d_in[7], (cbf)d_in[8], (__nv_bfloat16*)d_out);
        return;
    }
    Params P;
    enc2d(enc, &P.x, d_in[0], S_, D_, 128);
    enc2d(enc, &P.cr, d_in[1], S_, S_, 128);
    enc2d(enc, &P.ci, d_in[2], S_, S_, 128);
    enc2d(enc, &P.wr, d_in[3], D_, D_, 64);
    enc2d(enc, &P.wi, d_in[4], D_, D_, 64);
    enc2d(enc, &P.w1, d_in[6], D_, F_, 32);
    enc2d(enc, &P.w2, d_in[7], F_, D_, 64);
    enc2d(enc, &P.out, d_out, S_, D_, 64);
    fused_kernel<<<128, 384, SMEM_BYTES>>>(P, (cbf)d_in[8], (__nv_bfloat16*)d_out, (const unsigned char*)d_in[7]);
}
```
